```python
import torch

def _softmax(x, axis=-1):
    return torch.softmax(x, dim=axis)
def _gelu(x):
    return torch.nn.functional.gelu(x, approximate="tanh")
def _silu(x):
    return torch.nn.functional.silu(x)
def _sigmoid(x):
    return torch.sigmoid(x)
def _layernorm(x, axis=-1, eps=1e-5):
    m = x.mean(dim=axis, keepdim=True)
    v = x.var(dim=axis, keepdim=True, unbiased=False)
    return (x - m) / torch.sqrt(v + eps)
def _scatter_add(tgt, idx, src, axis=0):
    return tgt.clone().index_add_(axis, idx, src)
def _segment_sum(src, seg, n):
    out = torch.zeros((n,) + src.shape[1:], dtype=src.dtype)
    return out.index_add_(0, seg, src)
def _pad(x, pw):
    flat = tuple(v for pair in reversed(pw) for v in pair)
    return torch.nn.functional.pad(x, flat)

kernel_name = 'concat_heads__mha_block_cached__gqa_block_cached__near_ridge'

def setup_inputs():

    _w = (lambda a: (lambda t: t.to(torch.bfloat16) if t.is_floating_point() else t)(torch.as_tensor(a)))
    def _A_setup():
        B, Sq, D = 8, 128, 512
        H, Sk, Dh = 32, 1024, 128
        return {
            "x": _w((lambda *s: torch.randn(*s, dtype=torch.bfloat16) * 0.8)(B, Sq, D)),
            "k_cache": _w((lambda *s: torch.randn(*s, dtype=torch.bfloat16) * 0.8)(B, H, Sk, Dh)),
            "v_cache": _w((lambda *s: torch.randn(*s, dtype=torch.bfloat16) * 0.05)(B, H, Sk, Dh)),
            "wq": _w((lambda *s: torch.randn(*s, dtype=torch.bfloat16) * 0.8)(D, H * Dh) * (D ** -0.5)),
            "wo": _w((lambda *s: torch.randn(*s, dtype=torch.bfloat16) * 0.05)(H * Dh, D) * ((H * Dh) ** -0.5)),
        }
    _A_in = _A_setup()

    def _B_setup():
        B, Sq, D = 8, 128, 512
        Hq, Hkv, Sk, Dh = 32, 32, 1024, 128
        assert Hq % Hkv == 0, (Hq, Hkv)
        return {
            "x": _w((lambda *s: torch.randn(*s, dtype=torch.bfloat16) * 0.8)(B, Sq, D)),
            "k_cache": _w((lambda *s: torch.randn(*s, dtype=torch.bfloat16) * 0.8)(B, Hkv, Sk, Dh)),
            "v_cache": _w((lambda *s: torch.randn(*s, dtype=torch.bfloat16) * 0.05)(B, Hkv, Sk, Dh)),
            "wq": _w((lambda *s: torch.randn(*s, dtype=torch.bfloat16) * 0.8)(D, Hq * Dh) * (D ** -0.5)),
            "wo": _w((lambda *s: torch.randn(*s, dtype=torch.bfloat16) * 0.05)(Hq * Dh, D) * ((Hq * Dh) ** -0.5)),
        }
    _B_in = _B_setup()

    return {
        "A_x": _A_in["x"],
        "A_k_cache": _A_in["k_cache"],
        "A_v_cache": _A_in["v_cache"],
        "A_wq": _A_in["wq"],
        "A_wo": _A_in["wo"],
        "B_x": _B_in["x"],
        "B_k_cache": _B_in["k_cache"],
        "B_v_cache": _B_in["v_cache"],
        "B_wq": _B_in["wq"],
        "B_wo": _B_in["wo"],
    }

def reference(A_x, A_k_cache, A_v_cache, A_wq, A_wo, B_x, B_k_cache, B_v_cache, B_wq, B_wo):
    def _A_ref(x, k_cache, v_cache, wq, wo):
        B, Sq, D = x.shape
        H, Dh = 32, 128
        q = (lambda x, *d: x.permute(*d))((x @ wq).reshape(B, Sq, H, Dh), 0, 2, 1, 3)
        scores = torch.einsum("bhqd,bhkd->bhqk", q, k_cache) * (Dh ** -0.5)
        p = _softmax(scores, axis=-1)
        o = torch.einsum("bhqk,bhkd->bhqd", p, v_cache)
        return (lambda x, *d: x.permute(*d))(o, 0, 2, 1, 3).reshape(B, Sq, H * Dh) @ wo

    def _B_ref(x, k_cache, v_cache, wq, wo):
        B, Sq, D = x.shape
        Hq, Dh = 32, 128
        Hkv = k_cache.shape[1]
        rep = Hq // Hkv
        q = (lambda x, *d: x.permute(*d))((x @ wq).reshape(B, Sq, Hq, Dh), 0, 2, 1, 3)
        k = (lambda x, n, axis: torch.repeat_interleave(x, n, dim=axis))(k_cache, rep, axis=1)
        v = (lambda x, n, axis: torch.repeat_interleave(x, n, dim=axis))(v_cache, rep, axis=1)
        scores = torch.einsum("bhqd,bhkd->bhqk", q, k) * (Dh ** -0.5)
        p = _softmax(scores, axis=-1)
        o = torch.einsum("bhqk,bhkd->bhqd", p, v)
        return (lambda x, *d: x.permute(*d))(o, 0, 2, 1, 3).reshape(B, Sq, Hq * Dh) @ wo

    a = _A_ref(A_x, A_k_cache, A_v_cache, A_wq, A_wo)
    b = _B_ref(B_x, B_k_cache, B_v_cache, B_wq, B_wo)
    return torch.concatenate([a, b], axis=-1)
```

```cpp
#include <cuda_runtime.h>
#include <cuda_bf16.h>
#include <cuda.h>
#include <stdint.h>
#include <stdio.h>

namespace {

constexpr int NB = 8;
constexpr int SQ = 128;
constexpr int DM = 512;
constexpr int NH = 32;
constexpr int SK = 1024;
constexpr int DH = 128;
constexpr int N_ITEMS = 2 * NB * NH;

constexpr int NSTAGES = 6;
constexpr int STAGE_BYTES = 32768;
constexpr int NUM_THREADS = 384;
constexpr int Q_BYTES = 32768;
constexpr int SMEM_BYTES = NSTAGES * STAGE_BYTES + Q_BYTES + 1024   + 256  ;

struct TmaMaps {
    CUtensorMap x[2], wq[2], k[2], v[2], wo[2];
};

__device__ __nv_bfloat16 g_o[2 * NB * SQ * NH * DH];
__device__ float g_part[4 * 2 * NB * SQ * DM];
__device__ unsigned int g_cnt[2 * NB * 2];

__device__ __forceinline__ uint32_t smem_u32(const void* p) { return (uint32_t)__cvta_generic_to_shared(p); }

__device__ __forceinline__ void mbar_init(uint32_t bar, uint32_t count) {
    asm volatile("mbarrier.init.shared::cta.b64 [%0], %1;" :: "r"(bar), "r"(count) : "memory");
}
__device__ __forceinline__ void mbar_expect_tx(uint32_t bar, uint32_t bytes) {
    asm volatile("mbarrier.arrive.expect_tx.shared::cta.b64 _, [%0], %1;" :: "r"(bar), "r"(bytes) : "memory");
}
__device__ __forceinline__ void mbar_arrive(uint32_t bar) {
    asm volatile("mbarrier.arrive.shared::cta.b64 _, [%0];" :: "r"(bar) : "memory");
}
__device__ __forceinline__ bool mbar_try_wait(uint32_t bar, uint32_t parity) {
    uint32_t ok;
    asm volatile(
        "{\n.reg .pred p;\n"
        "mbarrier.try_wait.parity.shared::cta.b64 p, [%1], %2;\n"
        "selp.u32 %0, 1, 0, p;\n}\n" : "=r"(ok) : "r"(bar), "r"(parity) : "memory");
    return ok != 0;
}
__device__ __forceinline__ void mbar_wait(uint32_t bar, uint32_t parity) {
    while (!mbar_try_wait(bar, parity)) { }
}
__device__ __forceinline__ void tma_load_2d(uint32_t dst, const CUtensorMap* map, int c0, int c1, uint32_t bar) {
    asm volatile(
        "cp.async.bulk.tensor.2d.shared::cluster.global.mbarrier::complete_tx::bytes [%0], [%1, {%3, %4}], [%2];"
        :: "r"(dst), "l"(map), "r"(bar), "r"(c0), "r"(c1) : "memory");
}
__device__ __forceinline__ void tma_load_2d_hint(uint32_t dst, const CUtensorMap* map, int c0, int c1, uint32_t bar, uint64_t pol) {
    asm volatile(
        "cp.async.bulk.tensor.2d.shared::cluster.global.mbarrier::complete_tx::bytes.L2::cache_hint [%0], [%1, {%3, %4}], [%2], %5;"
        :: "r"(dst), "l"(map), "r"(bar), "r"(c0), "r"(c1), "l"(pol) : "memory");
}
__device__ __forceinline__ void wgmma_fence() { asm volatile("wgmma.fence.sync.aligned;" ::: "memory"); }
__device__ __forceinline__ void wgmma_commit() { asm volatile("wgmma.commit_group.sync.aligned;" ::: "memory"); }
template <int N> __device__ __forceinline__ void wgmma_wait() { asm volatile("wgmma.wait_group.sync.aligned %0;" :: "n"(N) : "memory"); }

__device__ __forceinline__ uint64_t make_desc(uint32_t addr, uint32_t lbo, uint32_t sbo) {
    return (uint64_t)((addr & 0x3FFFF) >> 4) | ((uint64_t)(lbo >> 4) << 16) | ((uint64_t)(sbo >> 4) << 32) | (1ull << 62);
}

#define ACC_REGS_64                                                                                   \
    "{%0, %1, %2, %3, %4, %5, %6, %7, %8, %9, %10, %11, %12, %13, %14, %15, "                         \
    "%16, %17, %18, %19, %20, %21, %22, %23, %24, %25, %26, %27, %28, %29, %30, %31, "                \
    "%32, %33, %34, %35, %36, %37, %38, %39, %40, %41, %42, %43, %44, %45, %46, %47, "                \
    "%48, %49, %50, %51, %52, %53, %54, %55, %56, %57, %58, %59, %60, %61, %62, %63}"
#define ACC_OPS_64(d)                                                                                 \
    "+f"(d[0]), "+f"(d[1]), "+f"(d[2]), "+f"(d[3]), "+f"(d[4]), "+f"(d[5]), "+f"(d[6]), "+f"(d[7]),   \
    "+f"(d[8]), "+f"(d[9]), "+f"(d[10]), "+f"(d[11]), "+f"(d[12]), "+f"(d[13]), "+f"(d[14]), "+f"(d[15]), \
    "+f"(d[16]), "+f"(d[17]), "+f"(d[18]), "+f"(d[19]), "+f"(d[20]), "+f"(d[21]), "+f"(d[22]), "+f"(d[23]), \
    "+f"(d[24]), "+f"(d[25]), "+f"(d[26]), "+f"(d[27]), "+f"(d[28]), "+f"(d[29]), "+f"(d[30]), "+f"(d[31]), \
    "+f"(d[32]), "+f"(d[33]), "+f"(d[34]), "+f"(d[35]), "+f"(d[36]), "+f"(d[37]), "+f"(d[38]), "+f"(d[39]), \
    "+f"(d[40]), "+f"(d[41]), "+f"(d[42]), "+f"(d[43]), "+f"(d[44]), "+f"(d[45]), "+f"(d[46]), "+f"(d[47]), \
    "+f"(d[48]), "+f"(d[49]), "+f"(d[50]), "+f"(d[51]), "+f"(d[52]), "+f"(d[53]), "+f"(d[54]), "+f"(d[55]), \
    "+f"(d[56]), "+f"(d[57]), "+f"(d[58]), "+f"(d[59]), "+f"(d[60]), "+f"(d[61]), "+f"(d[62]), "+f"(d[63])

template <int TNSPB>
__device__ __forceinline__ void wgmma_ss(float (&d)[64], uint64_t da, uint64_t db, int accum) {
    asm volatile(
        "{\n.reg .pred p;\nsetp.ne.b32 p, %66, 0;\n"
        "wgmma.mma_async.sync.aligned.m64n128k16.f32.bf16.bf16 " ACC_REGS_64 ", %64, %65, p, 1, 1, 0, %67;\n}\n"
        : ACC_OPS_64(d) : "l"(da), "l"(db), "r"(accum), "n"(TNSPB));
}
template <int TNSPB>
__device__ __forceinline__ void wgmma_rs(float (&d)[64], uint32_t a0, uint32_t a1, uint32_t a2, uint32_t a3, uint64_t db, int accum) {
    asm volatile(
        "{\n.reg .pred p;\nsetp.ne.b32 p, %69, 0;\n"
        "wgmma.mma_async.sync.aligned.m64n128k16.f32.bf16.bf16 " ACC_REGS_64 ", {%64, %65, %66, %67}, %68, p, 1, 1, %70;\n}\n"
        : ACC_OPS_64(d) : "r"(a0), "r"(a1), "r"(a2), "r"(a3), "l"(db), "r"(accum), "n"(TNSPB));
}

__device__ __forceinline__ uint32_t pack_bf16(float lo, float hi) {
    uint32_t r;
    asm("cvt.rn.bf16x2.f32 %0, %1, %2;" : "=r"(r) : "f"(hi), "f"(lo));
    return r;
}
__device__ __forceinline__ float ex2(float x) {
    float y;
    asm("ex2.approx.ftz.f32 %0, %1;" : "=f"(y) : "f"(x));
    return y;
}

struct Ring {
    int stage;
    uint32_t phase;
    int n = NSTAGES;
    __device__ __forceinline__ void next() {
        if (++stage == n) { stage = 0; phase ^= 1; }
    }
};

__global__ void __launch_bounds__(NUM_THREADS, 1)
fused_attn_kernel(const __grid_constant__ TmaMaps maps, __nv_bfloat16* __restrict__ out)
{
    extern __shared__ uint8_t smem_raw[];
    const uint32_t smem_base = (smem_u32(smem_raw) + 1023u) & ~1023u;
    const uint32_t q_base = smem_base + NSTAGES * STAGE_BYTES;
    const uint32_t bar_base = q_base + Q_BYTES;
    auto full_bar = [&](int s) { return bar_base + 8 * s; };
    auto empty_bar = [&](int s) { return bar_base + 8 * (NSTAGES + s); };
    __shared__ unsigned int s_flag;

    const int tid = threadIdx.x;
    const int wg = tid >> 7;

    if (tid == 0) {
        for (int s = 0; s < NSTAGES; s++) {
            mbar_init(full_bar(s), 1);
            mbar_init(empty_bar(s), 8);
        }
        asm volatile("fence.mbarrier_init.release.cluster;" ::: "memory");
    }
    __syncthreads();

    if (wg == 0) {
        asm volatile("setmaxnreg.dec.sync.aligned.u32 40;");
        if (tid == 0) {
            uint64_t pol;
            asm volatile("createpolicy.fractional.L2::evict_first.b64 %0, 1.0;" : "=l"(pol));
            Ring r{0, 1};
            for (int item = blockIdx.x; item < N_ITEMS; item += gridDim.x) {
                const int br = item / (NB * NH);
                const int b = (item / NH) % NB;
                const int h = item % NH;
                for (int kc = 0; kc < 8; kc++) {
                    mbar_wait(empty_bar(r.stage), r.phase);
                    const uint32_t dst = smem_base + r.stage * STAGE_BYTES;
                    mbar_expect_tx(full_bar(r.stage), STAGE_BYTES);
                    tma_load_2d(dst, &maps.x[br], kc * 64, b * SQ, full_bar(r.stage));
                    tma_load_2d(dst + 16384, &maps.wq[br], h * DH, kc * 64, full_bar(r.stage));
                    tma_load_2d(dst + 24576, &maps.wq[br], h * DH + 64, kc * 64, full_bar(r.stage));
                    r.next();
                }
                const int row0 = (b * NH + h) * SK;
                for (int j = 0; j < SK / 128; j++) {
                    mbar_wait(empty_bar(r.stage), r.phase);
                    uint32_t dst = smem_base + r.stage * STAGE_BYTES;
                    mbar_expect_tx(full_bar(r.stage), STAGE_BYTES);
                    tma_load_2d_hint(dst, &maps.k[br], 0, row0 + j * 128, full_bar(r.stage), pol);
                    tma_load_2d_hint(dst + 16384, &maps.k[br], 64, row0 + j * 128, full_bar(r.stage), pol);
                    r.next();
                    mbar_wait(empty_bar(r.stage), r.phase);
                    dst = smem_base + r.stage * STAGE_BYTES;
                    mbar_expect_tx(full_bar(r.stage), STAGE_BYTES);
                    tma_load_2d_hint(dst, &maps.v[br], 0, row0 + j * 128, full_bar(r.stage), pol);
                    tma_load_2d_hint(dst + 16384, &maps.v[br], 64, row0 + j * 128, full_bar(r.stage), pol);
                    r.next();
                }
            }
        }
    } else {
        asm volatile("setmaxnreg.inc.sync.aligned.u32 232;");
        const int cw = wg - 1;
        const int warp = (tid >> 5) & 3;
        const int lane = tid & 31;
        const float scale_log2 = 0.08838834764831845f * 1.4426950408889634f;
        Ring r{0, 0};

        float acc[64];
        float o[64];
        uint32_t afrag[32];

        for (int item = blockIdx.x; item < N_ITEMS; item += gridDim.x) {
            const int br = item / (NB * NH);
            const int b = (item / NH) % NB;

            for (int kc = 0; kc < 8; kc++) {
                mbar_wait(full_bar(r.stage), r.phase);
                const uint32_t base = smem_base + r.stage * STAGE_BYTES;
                const uint64_t da = make_desc(base + cw * 8192, 16, 1024);
                const uint64_t db = make_desc(base + 16384, 8192, 1024);
                wgmma_fence();
                #pragma unroll
                for (int kk = 0; kk < 4; kk++)
                    wgmma_ss<1>(acc, da + (uint64_t)(kk * 32 >> 4), db + (uint64_t)(kk * 2048 >> 4), (kc | kk) != 0);
                wgmma_commit();
                wgmma_wait<0>();
                if (lane == 0) mbar_arrive(empty_bar(r.stage));
                r.next();
            }
            {
                const int row = cw * 64 + warp * 16 + (lane >> 2);
                const uint32_t qrow = q_base + row * 128 + (lane & 3) * 4;
                #pragma unroll
                for (int i = 0; i < 16; i++) {
                    const uint32_t addr = qrow + (i >> 3) * 16384 + (((i & 7) ^ (row & 7)) << 4);
                    asm volatile("st.shared.b32 [%0], %1;" :: "r"(addr), "r"(pack_bf16(acc[4 * i], acc[4 * i + 1])) : "memory");
                    asm volatile("st.shared.b32 [%0], %1;" :: "r"(addr + 1024), "r"(pack_bf16(acc[4 * i + 2], acc[4 * i + 3])) : "memory");
                }
                asm volatile("fence.proxy.async.shared::cta;" ::: "memory");
                asm volatile("bar.sync %0, 128;" :: "r"(2 + cw) : "memory");
            }

            float m0 = -INFINITY, m1 = -INFINITY, l0 = 0.f, l1 = 0.f;
            #pragma unroll
            for (int i = 0; i < 64; i++) o[i] = 0.f;

            for (int j = 0; j < SK / 128; j++) {
                mbar_wait(full_bar(r.stage), r.phase);
                {
                    const uint32_t base = smem_base + r.stage * STAGE_BYTES;
                    const uint64_t db = make_desc(base, 16, 1024);
                    wgmma_fence();
                    const uint64_t dq = make_desc(q_base + cw * 8192, 16, 1024);
                    #pragma unroll
                    for (int kk = 0; kk < 8; kk++) {
                        const uint64_t off = (uint64_t)(((kk >> 2) * 16384 + (kk & 3) * 32) >> 4);
                        wgmma_ss<0>(acc, dq + off, db + off, kk != 0);
                    }
                    wgmma_commit();
                    wgmma_wait<0>();
                    if (lane == 0) mbar_arrive(empty_bar(r.stage));
                    r.next();
                }
                float mx0 = acc[0], mx1 = acc[2];
                #pragma unroll
                for (int i = 0; i < 16; i++) {
                    mx0 = fmaxf(mx0, fmaxf(acc[4 * i], acc[4 * i + 1]));
                    mx1 = fmaxf(mx1, fmaxf(acc[4 * i + 2], acc[4 * i + 3]));
                }
                mx0 = fmaxf(mx0, __shfl_xor_sync(0xffffffffu, mx0, 1));
                mx1 = fmaxf(mx1, __shfl_xor_sync(0xffffffffu, mx1, 1));
                mx0 = fmaxf(mx0, __shfl_xor_sync(0xffffffffu, mx0, 2));
                mx1 = fmaxf(mx1, __shfl_xor_sync(0xffffffffu, mx1, 2));
                const float mn0 = fmaxf(m0, mx0 * scale_log2);
                const float mn1 = fmaxf(m1, mx1 * scale_log2);
                const float a0 = ex2(m0 - mn0);
                const float a1 = ex2(m1 - mn1);
                m0 = mn0; m1 = mn1;
                float s0 = 0.f, s1 = 0.f;
                #pragma unroll
                for (int i = 0; i < 16; i++) {
                    const float p0 = ex2(fmaf(acc[4 * i], scale_log2, -mn0));
                    const float p1 = ex2(fmaf(acc[4 * i + 1], scale_log2, -mn0));
                    const float p2 = ex2(fmaf(acc[4 * i + 2], scale_log2, -mn1));
                    const float p3 = ex2(fmaf(acc[4 * i + 3], scale_log2, -mn1));
                    s0 += p0 + p1;
                    s1 += p2 + p3;
                    afrag[2 * i] = pack_bf16(p0, p1);
                    afrag[2 * i + 1] = pack_bf16(p2, p3);
                }
                l0 = l0 * a0 + s0;
                l1 = l1 * a1 + s1;
                #pragma unroll
                for (int i = 0; i < 16; i++) {
                    o[4 * i] *= a0; o[4 * i + 1] *= a0;
                    o[4 * i + 2] *= a1; o[4 * i + 3] *= a1;
                }
                mbar_wait(full_bar(r.stage), r.phase);
                {
                    const uint32_t base = smem_base + r.stage * STAGE_BYTES;
                    const uint64_t db = make_desc(base, 16384, 1024);
                    wgmma_fence();
                    #pragma unroll
                    for (int kk = 0; kk < 8; kk++)
                        wgmma_rs<1>(o, afrag[4 * kk], afrag[4 * kk + 1], afrag[4 * kk + 2], afrag[4 * kk + 3],
                                    db + (uint64_t)(kk * 2048 >> 4), 1);
                    wgmma_commit();
                    wgmma_wait<0>();
                    if (lane == 0) mbar_arrive(empty_bar(r.stage));
                    r.next();
                }
            }
            l0 += __shfl_xor_sync(0xffffffffu, l0, 1);
            l1 += __shfl_xor_sync(0xffffffffu, l1, 1);
            l0 += __shfl_xor_sync(0xffffffffu, l0, 2);
            l1 += __shfl_xor_sync(0xffffffffu, l1, 2);
            const float i0 = 1.f / l0, i1 = 1.f / l1;
            #pragma unroll
            for (int i = 0; i < 16; i++) {
                afrag[2 * i] = pack_bf16(o[4 * i] * i0, o[4 * i + 1] * i0);
                afrag[2 * i + 1] = pack_bf16(o[4 * i + 2] * i1, o[4 * i + 3] * i1);
            }
            {
                const int h = item % NH;
                __nv_bfloat16* dst = g_o + ((size_t)(br * NB + b) * SQ + cw * 64 + warp * 16 + (lane >> 2)) * (NH * DH) + h * DH + (lane & 3) * 2;
                #pragma unroll
                for (int i = 0; i < 16; i++) {
                    *reinterpret_cast<uint32_t*>(dst + i * 8) = afrag[2 * i];
                    *reinterpret_cast<uint32_t*>(dst + 8 * (NH * DH) + i * 8) = afrag[2 * i + 1];
                }
            }
        }
    }
}

constexpr int G_NSTAGES = 4;
constexpr int G_STAGE_BYTES = 16384 + 32768;
constexpr int G_SMEM_BYTES = G_NSTAGES * G_STAGE_BYTES + 1024 + 256;

#define ACC_REGS_128                                                                                  \
    "{%0, %1, %2, %3, %4, %5, %6, %7, %8, %9, %10, %11, %12, %13, %14, %15, "                         \
    "%16, %17, %18, %19, %20, %21, %22, %23, %24, %25, %26, %27, %28, %29, %30, %31, "                \
    "%32, %33, %34, %35, %36, %37, %38, %39, %40, %41, %42, %43, %44, %45, %46, %47, "                \
    "%48, %49, %50, %51, %52, %53, %54, %55, %56, %57, %58, %59, %60, %61, %62, %63, "                \
    "%64, %65, %66, %67, %68, %69, %70, %71, %72, %73, %74, %75, %76, %77, %78, %79, "                \
    "%80, %81, %82, %83, %84, %85, %86, %87, %88, %89, %90, %91, %92, %93, %94, %95, "                \
    "%96, %97, %98, %99, %100, %101, %102, %103, %104, %105, %106, %107, %108, %109, %110, %111, "   \
    "%112, %113, %114, %115, %116, %117, %118, %119, %120, %121, %122, %123, %124, %125, %126, %127}"
#define ACC_OPS_128(d) ACC_OPS_64(d), ACC_OPS_64((d + 64))

__device__ __forceinline__ void wgmma_ss_n256(float (&d)[128], uint64_t da, uint64_t db, int accum) {
    asm volatile(
        "{\n.reg .pred p;\nsetp.ne.b32 p, %130, 0;\n"
        "wgmma.mma_async.sync.aligned.m64n256k16.f32.bf16.bf16 " ACC_REGS_128 ", %128, %129, p, 1, 1, 0, 1;\n}\n"
        : ACC_OPS_128(d) : "l"(da), "l"(db), "r"(accum));
}

struct GemmMaps { CUtensorMap o[2], wo[2]; };

__global__ void __launch_bounds__(NUM_THREADS, 1)
outproj_kernel(const __grid_constant__ GemmMaps maps, __nv_bfloat16* __restrict__ out)
{
    extern __shared__ uint8_t smem_raw[];
    const uint32_t smem_base = (smem_u32(smem_raw) + 1023u) & ~1023u;
    const uint32_t bar_base = smem_base + G_NSTAGES * G_STAGE_BYTES;
    auto full_bar = [&](int s) { return bar_base + 8 * s; };
    auto empty_bar = [&](int s) { return bar_base + 8 * (G_NSTAGES + s); };
    __shared__ unsigned int s_flag;
    const int tid = threadIdx.x;
    const int wg = tid >> 7;
    const int kq = blockIdx.x & 3;
    const int nh = (blockIdx.x >> 2) & 1;
    const int bb = blockIdx.x >> 3;
    const int br = bb / NB;

    if (tid == 0) {
        for (int s = 0; s < G_NSTAGES; s++) {
            mbar_init(full_bar(s), 1);
            mbar_init(empty_bar(s), 8);
        }
        asm volatile("fence.mbarrier_init.release.cluster;" ::: "memory");
    }
    __syncthreads();

    if (wg == 0) {
        asm volatile("setmaxnreg.dec.sync.aligned.u32 40;");
        if (tid == 0) {
            Ring r{0, 1, G_NSTAGES};
            for (int ks = 0; ks < 16; ks++) {
                mbar_wait(empty_bar(r.stage), r.phase);
                const uint32_t dst = smem_base + r.stage * G_STAGE_BYTES;
                mbar_expect_tx(full_bar(r.stage), G_STAGE_BYTES);
                const int kc = kq * 1024 + ks * 64;
                tma_load_2d(dst, &maps.o[br], kc, (bb % NB) * SQ, full_bar(r.stage));
                #pragma unroll
                for (int q = 0; q < 4; q++)
                    tma_load_2d(dst + 16384 + q * 8192, &maps.wo[br], nh * 256 + q * 64, kc, full_bar(r.stage));
                r.next();
            }
        }
    } else {
        asm volatile("setmaxnreg.inc.sync.aligned.u32 232;");
        const int cw = wg - 1;
        const int warp = (tid >> 5) & 3;
        const int lane = tid & 31;
        Ring r{0, 0, G_NSTAGES};
        float acc[64], acc1[64];
        for (int ks = 0; ks < 16; ks++) {
            mbar_wait(full_bar(r.stage), r.phase);
            const uint32_t base = smem_base + r.stage * G_STAGE_BYTES;
            const uint64_t da = make_desc(base + cw * 8192, 16, 1024);
            const uint64_t db = make_desc(base + 16384, 8192, 1024);
            const uint64_t db1 = make_desc(base + 32768, 8192, 1024);
            wgmma_fence();
            #pragma unroll
            for (int kk = 0; kk < 4; kk++) {
                wgmma_ss<1>(acc, da + (uint64_t)(kk * 32 >> 4), db + (uint64_t)(kk * 2048 >> 4), (ks | kk) != 0);
                wgmma_ss<1>(acc1, da + (uint64_t)(kk * 32 >> 4), db1 + (uint64_t)(kk * 2048 >> 4), (ks | kk) != 0);
            }
            wgmma_commit();
            wgmma_wait<0>();
            if (lane == 0) mbar_arrive(empty_bar(r.stage));
            r.next();
        }
        float* part = g_part + (((size_t)kq * 2 * NB + bb) * SQ + cw * 64 + warp * 16 + (lane >> 2)) * DM + nh * 256 + (lane & 3) * 2;
        #pragma unroll
        for (int i = 0; i < 16; i++) {
            *reinterpret_cast<float2*>(part + i * 8) = make_float2(acc[4 * i], acc[4 * i + 1]);
            *reinterpret_cast<float2*>(part + 8 * DM + i * 8) = make_float2(acc[4 * i + 2], acc[4 * i + 3]);
            *reinterpret_cast<float2*>(part + 128 + i * 8) = make_float2(acc1[4 * i], acc1[4 * i + 1]);
            *reinterpret_cast<float2*>(part + 128 + 8 * DM + i * 8) = make_float2(acc1[4 * i + 2], acc1[4 * i + 3]);
        }
        __threadfence();
        asm volatile("bar.sync 1, 256;" ::: "memory");
        if (tid == 128) {
            const unsigned int prev = atomicAdd(&g_cnt[bb * 2 + nh], 1u);
            s_flag = (prev == 3) ? 1u : 0u;
        }
        asm volatile("bar.sync 1, 256;" ::: "memory");
        if (s_flag) {
            __threadfence();
            const int ct = tid - 128;
            const size_t tile = (size_t)bb * SQ * DM + nh * 256;
            for (int i = ct; i < SQ * 64; i += 256) {
                const int row = i >> 6, c4 = (i & 63) * 4;
                const float* p0 = g_part + tile + (size_t)row * DM + c4;
                float4 v = __ldcg(reinterpret_cast<const float4*>(p0));
                const float4 v1 = __ldcg(reinterpret_cast<const float4*>(p0 + (size_t)2 * NB * SQ * DM));
                const float4 v2 = __ldcg(reinterpret_cast<const float4*>(p0 + (size_t)4 * NB * SQ * DM));
                const float4 v3 = __ldcg(reinterpret_cast<const float4*>(p0 + (size_t)6 * NB * SQ * DM));
                v.x += v1.x + v2.x + v3.x; v.y += v1.y + v2.y + v3.y;
                v.z += v1.z + v2.z + v3.z; v.w += v1.w + v2.w + v3.w;
                uint2 pk;
                pk.x = pack_bf16(v.x, v.y);
                pk.y = pack_bf16(v.z, v.w);
                const int b = bb % NB;
                *reinterpret_cast<uint2*>(out + ((size_t)(b * SQ + row)) * (2 * DM) + br * DM + nh * 256 + c4) = pk;
            }
            if (tid == 128) g_cnt[bb * 2 + nh] = 0u;
        }
    }
}

typedef CUresult (*EncodeFn)(CUtensorMap*, CUtensorMapDataType, cuuint32_t, void*, const cuuint64_t*, const cuuint64_t*,
                             const cuuint32_t*, const cuuint32_t*, CUtensorMapInterleave, CUtensorMapSwizzle,
                             CUtensorMapL2promotion, CUtensorMapFloatOOBfill);

void make_map_2d(EncodeFn enc, CUtensorMap* m, const void* ptr, uint64_t rows, uint64_t cols, uint32_t box_rows, uint32_t box_cols) {
    cuuint64_t dims[2] = {cols, rows};
    cuuint64_t strides[1] = {cols * 2};
    cuuint32_t box[2] = {box_cols, box_rows};
    cuuint32_t estr[2] = {1, 1};
    enc(m, CU_TENSOR_MAP_DATA_TYPE_BFLOAT16, 2, const_cast<void*>(ptr), dims, strides, box, estr,
        CU_TENSOR_MAP_INTERLEAVE_NONE, CU_TENSOR_MAP_SWIZZLE_128B, CU_TENSOR_MAP_L2_PROMOTION_L2_256B,
        CU_TENSOR_MAP_FLOAT_OOB_FILL_NONE);
}

}

extern "C" void kernel_launch(void* const* d_in, const int* in_sizes, int n_in, void* d_out, int out_size) {
    (void)in_sizes; (void)n_in; (void)out_size;
    EncodeFn enc = nullptr;
    cudaDriverEntryPointQueryResult qres;
    cudaGetDriverEntryPoint("cuTensorMapEncodeTiled", (void**)&enc, cudaEnableDefault, &qres);

    TmaMaps maps;
    for (int br = 0; br < 2; br++) {
        const void* x = d_in[br * 5 + 0];
        const void* k = d_in[br * 5 + 1];
        const void* v = d_in[br * 5 + 2];
        const void* wq = d_in[br * 5 + 3];
        const void* wo = d_in[br * 5 + 4];
        make_map_2d(enc, &maps.x[br], x, NB * SQ, DM, 128, 64);
        make_map_2d(enc, &maps.wq[br], wq, DM, NH * DH, 64, 64);
        make_map_2d(enc, &maps.k[br], k, (uint64_t)NB * NH * SK, DH, 128, 64);
        make_map_2d(enc, &maps.v[br], v, (uint64_t)NB * NH * SK, DH, 128, 64);
        make_map_2d(enc, &maps.wo[br], wo, NH * DH, DM, 128, 64);
    }
    cudaFuncSetAttribute(fused_attn_kernel, cudaFuncAttributeMaxDynamicSharedMemorySize, SMEM_BYTES);
    int dev = 0, sms = 132;
    cudaGetDevice(&dev);
    cudaDeviceGetAttribute(&sms, cudaDevAttrMultiProcessorCount, dev);
    fused_attn_kernel<<<sms, NUM_THREADS, SMEM_BYTES>>>(maps, (__nv_bfloat16*)d_out);

    __nv_bfloat16* o_ptr = nullptr;
    cudaGetSymbolAddress((void**)&o_ptr, g_o);
    GemmMaps gm;
    for (int br = 0; br < 2; br++) {
        make_map_2d(enc, &gm.o[br], o_ptr + (size_t)br * NB * SQ * NH * DH, NB * SQ, NH * DH, 128, 64);
        make_map_2d(enc, &gm.wo[br], d_in[br * 5 + 4], NH * DH, DM, 64, 64);
    }
    cudaFuncSetAttribute(outproj_kernel, cudaFuncAttributeMaxDynamicSharedMemorySize, G_SMEM_BYTES);
    outproj_kernel<<<2 * NB * 2 * 4, NUM_THREADS, G_SMEM_BYTES>>>(gm, (__nv_bfloat16*)d_out);
}
```
